```python
import torch

def _softmax(x, axis=-1):
    return torch.softmax(x, dim=axis)
def _gelu(x):
    return torch.nn.functional.gelu(x, approximate="tanh")
def _silu(x):
    return torch.nn.functional.silu(x)
def _sigmoid(x):
    return torch.sigmoid(x)
def _layernorm(x, axis=-1, eps=1e-5):
    m = x.mean(dim=axis, keepdim=True)
    v = x.var(dim=axis, keepdim=True, unbiased=False)
    return (x - m) / torch.sqrt(v + eps)
def _scatter_add(tgt, idx, src, axis=0):
    return tgt.clone().index_add_(axis, idx, src)
def _segment_sum(src, seg, n):
    out = torch.zeros((n,) + src.shape[1:], dtype=src.dtype)
    return out.index_add_(0, seg, src)
def _pad(x, pw):
    flat = tuple(v for pair in reversed(pw) for v in pair)
    return torch.nn.functional.pad(x, flat)

kernel_name = 'sequential_preLN__sliding_local_dilated__dense_activation_relu__prompt'

def setup_inputs():

    _w = (lambda a: (lambda t: t.to(torch.bfloat16) if t.is_floating_point() else t)(torch.as_tensor(a)))
    def _A_setup():
        B, S, D = 1, 2048, 1024
        return {
            "x": _w((lambda *s: torch.randn(*s, dtype=torch.bfloat16) * 0.05)(B, S, D)),
            "wqkv": _w((lambda *s: torch.randn(*s, dtype=torch.bfloat16) * 0.05)(D, 3 * D)),
            "wo": _w((lambda *s: torch.randn(*s, dtype=torch.bfloat16) * 0.05)(D, D)),
        }
    _A_in = _A_setup()

    def _B_setup():
        B, S, D, Dff = 1, 2048, 1024, 3584
        return {
            "x": _w((lambda *s: torch.randn(*s, dtype=torch.bfloat16) * 0.05)(B, S, D)),
            "w1": _w((lambda *s: torch.randn(*s, dtype=torch.bfloat16) * 0.05)(D, Dff)),
            "w2": _w((lambda *s: torch.randn(*s, dtype=torch.bfloat16) * 0.05)(Dff, D)),
        }
    _B_in = _B_setup()

    return {
        "A_x": _A_in["x"],
        "A_wqkv": _A_in["wqkv"],
        "A_wo": _A_in["wo"],
        "B_x": _B_in["x"],
        "B_w1": _B_in["w1"],
        "B_w2": _B_in["w2"],
    }

def reference(A_x, A_wqkv, A_wo, B_x, B_w1, B_w2):
    def _A_ref(x, wqkv, wo):
        B, S, D = x.shape
        H = 32; Dh = D // H
        W, dil = 8, 2
        qkv = (lambda x, *d: x.permute(*d))((x @ wqkv).reshape(B, S, 3, H, Dh), 2, 0, 3, 1, 4)
        q, k, v = qkv[0], qkv[1], qkv[2]
        scale = Dh ** -0.5
        pos = torch.arange(S)
        off = torch.arange(W) * dil
        idx = pos[:, None] - off[None, :]
        mask = idx >= 0
        idx_c = torch.where(mask, idx, 0).reshape(-1)
        kg = k[:, :, idx_c, :].reshape(B, H, S, W, Dh)
        vg = v[:, :, idx_c, :].reshape(B, H, S, W, Dh)
        logits = torch.einsum("bhsd,bhswd->bhsw", q, kg) * scale
        logits = torch.where(mask[None, None, :, :], logits, -1e9)
        attn = _softmax(logits, axis=-1)
        o = torch.einsum("bhsw,bhswd->bhsd", attn, vg)
        return (lambda x, *d: x.permute(*d))(o, 0, 2, 1, 3).reshape(B, S, D) @ wo

    def _B_ref(x, w1, w2):
        h = torch.einsum("bsd,df->bsf", x, w1)
        zero = torch.zeros_like(h)
        h = torch.maximum(h, zero)
        return torch.einsum("bsf,fd->bsd", h, w2)

    x = A_x
    h = x + _A_ref(_layernorm(x, axis=-1), A_wqkv, A_wo)
    h2 = h + _B_ref(_layernorm(h, axis=-1), B_w1, B_w2)
    return h2
```

```cpp
#include <cuda_runtime.h>
#include <cuda_bf16.h>
#include <cuda.h>
#include <stdint.h>

namespace {

typedef __nv_bfloat16 bf16;

#define H2 1
#define SY 4
#define R6 1
#define OS 1
#define HP 2
#define EP 1
#define S5 2
#define XC 0
#define PFN 2
constexpr int UNIT = 8192;
constexpr int RING_UNITS = 20;
constexpr int HEAD0 = S5 ? 0 : 10;
constexpr uint32_t OFF_S = RING_UNITS * UNIT;
constexpr uint32_t OFF_K = OFF_S + 16384 + 1024;
constexpr uint32_t OFF_V = OFF_K + 16384 + 1024;
constexpr uint32_t OFF_Q = OFF_V + 16384;
constexpr uint32_t OFF_TAG = OFF_S + 65536 - 16;
constexpr uint32_t OFF_AUX = OFF_S + 65536;
constexpr uint32_t OFF_MEAN = OFF_AUX;
constexpr uint32_t OFF_RSTD = OFF_AUX + 512;
constexpr uint32_t OFF_CS = OFF_AUX + 1024;
constexpr uint32_t OFF_BAR = OFF_AUX + 2816;
constexpr uint32_t BAR_FULL = OFF_BAR;
constexpr uint32_t BAR_EMPTY = OFF_BAR + 64;
constexpr uint32_t BAR_OATT = OFF_BAR + 128;
constexpr uint32_t BAR_E2C = OFF_BAR + 136;
constexpr uint32_t BAR_ID = OFF_BAR + 144;
constexpr uint32_t BAR_DUMPS = OFF_BAR + 160;
constexpr uint32_t BAR_SFREE = OFF_BAR + 176;
constexpr uint32_t BAR_RESX = OFF_BAR + 192;
constexpr uint32_t BAR_RESH = OFF_BAR + 200;
constexpr uint32_t BAR_O2 = OFF_BAR + 216;
constexpr uint32_t BAR_OFREE = OFF_BAR + 224;
constexpr uint32_t BAR_QKV = OFF_BAR + 232;
constexpr uint32_t BAR_DUMPH = OFF_BAR + 240;
constexpr int SMEM_BYTES = OFF_AUX + 3072;
constexpr float ATT_SC = 0.17677669529663687f * 1.4426950408889634f;
constexpr uint32_t SPIN_LIMIT = 1u << 24;

__device__ __align__(1024) uint8_t g_h[16 * 16 * 16384];
__device__ __align__(1024) uint8_t g_H[16 * 56 * 16384];
__device__ __align__(128) uint32_t g_flags[16 * 3 * 32];
__device__ __align__(128) uint4 g_stats[2048];
__device__ __align__(128) uint4 g_cs[8 * 16 * 128];
__device__ __align__(128) uint4 g_cs2[3 * 8 * 128];
__device__ __align__(128) uint2 g_halo[(128 + 16) * 512];
__device__ __align__(128) uint32_t g_sync[8 * 4 * 32];
__device__ uint32_t g_epoch[160];
#define PROF(idx)
#define PROFG(idx)
#define TRACE(k, i)

__device__ __forceinline__ void mbar_init(uint32_t bar, uint32_t cnt) { asm volatile("mbarrier.init.shared::cta.b64 [%0], %1;" :: "r"(bar), "r"(cnt) : "memory"); }
__device__ __forceinline__ void mbar_expect_tx(uint32_t bar, uint32_t bytes) { asm volatile("mbarrier.arrive.expect_tx.shared::cta.b64 _, [%0], %1;" :: "r"(bar), "r"(bytes) : "memory"); }
__device__ __forceinline__ void mbar_arrive(uint32_t bar) { asm volatile("mbarrier.arrive.shared::cta.b64 _, [%0];" :: "r"(bar) : "memory"); }
__device__ __forceinline__ void mbar_arrive_n(uint32_t bar, uint32_t n) { asm volatile("mbarrier.arrive.shared::cta.b64 _, [%0], %1;" :: "r"(bar), "r"(n) : "memory"); }
__device__ __forceinline__ void arrive_elect(uint32_t bar, uint32_t n) {
  asm volatile("{\n.reg .pred p;\nelect.sync _|p, 0xffffffff;\n@p mbarrier.arrive.shared::cta.b64 _, [%0], %1;\n}" :: "r"(bar), "r"(n) : "memory");
}
__device__ __forceinline__ void issue_tma3d(uint32_t dst, const CUtensorMap* m, uint32_t bar, uint32_t bytes, int c0, int c1, int c2) {
  asm volatile("{\n.reg .pred p;\nelect.sync _|p, 0xffffffff;\n@p mbarrier.arrive.expect_tx.shared::cta.b64 _, [%2], %6;\n"
    "@p cp.async.bulk.tensor.3d.shared::cluster.global.mbarrier::complete_tx::bytes [%0], [%1, {%3, %4, %5}], [%2];\n}"
    :: "r"(dst), "l"(m), "r"(bar), "r"(c0), "r"(c1), "r"(c2), "r"(bytes) : "memory");
}
__device__ __forceinline__ void complete_elect(uint32_t bar, uint32_t bytes) {
  asm volatile("{\n.reg .pred p;\nelect.sync _|p, 0xffffffff;\n@p mbarrier.complete_tx.relaxed.cta.shared::cta.b64 [%0], %1;\n}" :: "r"(bar), "r"(bytes) : "memory");
}
#define STEP_WAIT "{\n.reg .pred p;\n.reg .b32 c;\nmov.b32 c, 0;\nLAB_WAIT:\nmbarrier.try_wait.parity.shared::cta.b64 p, [%0], %1;\n@p bra DONE;\n" \
  "add.u32 c, c, 1;\nsetp.lt.u32 p, c, 0x1000000;\n@p bra LAB_WAIT;\ntrap;\nDONE:\nelect.sync _|p, 0xffffffff;\n"
__device__ __forceinline__ void step_bulk(uint32_t sb, uint32_t t, uint32_t off, const void* src, uint32_t bytes) {
  asm volatile(STEP_WAIT "@p mbarrier.arrive.expect_tx.shared::cta.b64 _, [%2], 16384;\n"
    "@p cp.async.bulk.shared::cluster.global.mbarrier::complete_tx::bytes [%3], [%4], %5, [%2];\n}"
    :: "r"(sb + BAR_EMPTY + (t & 0x38)), "r"(t >> 31), "r"(sb + BAR_FULL + ((t >> 6) & 0x38)), "r"(sb + off + (t & 0x3e000)), "l"(src), "r"(bytes) : "memory");
}
__device__ __forceinline__ void step_tma(uint32_t sb, uint32_t t, const CUtensorMap* m, uint32_t bytes, int c0, int c1, int c2) {
  asm volatile(STEP_WAIT "@p mbarrier.arrive.expect_tx.shared::cta.b64 _, [%2], %5;\n"
    "@p cp.async.bulk.tensor.3d.shared::cluster.global.mbarrier::complete_tx::bytes [%3], [%4, {%6, %7, %8}], [%2];\n}"
    :: "r"(sb + BAR_EMPTY + (t & 0x38)), "r"(t >> 31), "r"(sb + BAR_FULL + ((t >> 6) & 0x38)), "r"(sb + (t & 0x3e000)), "l"(m), "r"(bytes),
       "r"(c0), "r"(c1), "r"(c2) : "memory");
}
__device__ __forceinline__ void step_arm(uint32_t sb, uint32_t t, uint32_t bytes) {
  asm volatile(STEP_WAIT "@p mbarrier.arrive.expect_tx.shared::cta.b64 _, [%2], %3;\n}"
    :: "r"(sb + BAR_EMPTY + (t & 0x38)), "r"(t >> 31), "r"(sb + BAR_FULL + ((t >> 6) & 0x38)), "r"(bytes) : "memory");
}
__device__ __forceinline__ uint32_t peer(uint32_t a) {
  uint32_t r;
  asm("{\n.reg .b32 k;\nmov.u32 k, %%cluster_ctarank;\nxor.b32 k, k, 1;\nmapa.shared::cluster.u32 %0, %1, k;\n}" : "=r"(r) : "r"(a));
  return r;
}
__device__ __forceinline__ void peer_push(uint32_t dst, uint32_t src, uint32_t bytes, uint32_t bar) {
  asm volatile("{\n.reg .pred p;\nelect.sync _|p, 0xffffffff;\n@p cp.async.bulk.shared::cluster.shared::cta.mbarrier::complete_tx::bytes [%0], [%1], %2, [%3];\n}"
    :: "r"(peer(dst)), "r"(src), "r"(bytes), "r"(peer(bar)) : "memory");
}
__device__ __forceinline__ bool is_paired(uint32_t sb) {
  uint64_t a, b;
  asm volatile("barrier.cluster.wait.acquire.aligned;\nld.shared::cluster.u64 %0, [%2];\nld.shared.u64 %1, [%3];" : "=l"(a), "=l"(b) : "r"(peer(sb + BAR_ID)), "r"(sb + BAR_ID + 8) : "memory");
  return __all_sync(0xffffffffu, a == b);
}
__device__ __forceinline__ void release_elect(uint32_t bar, uint32_t bar2) {
  asm volatile("{\n.reg .pred p;\nelect.sync _|p, 0xffffffff;\n@p mbarrier.arrive.shared::cta.b64 _, [%0];\n@p mbarrier.arrive.shared::cluster.b64 _, [%1];\n}" :: "r"(bar), "r"(bar2) : "memory");
}
__device__ __forceinline__ void mbar_wait(uint32_t bar, uint32_t parity) {
  asm volatile("{\n.reg .pred p;\n.reg .b32 c;\nmov.b32 c, 0;\nLAB_WAIT:\nmbarrier.try_wait.parity.shared::cta.b64 p, [%0], %1;\n@p bra DONE;\n"
               "add.u32 c, c, 1;\nsetp.lt.u32 p, c, 0x1000000;\n@p bra LAB_WAIT;\ntrap;\nDONE:\n}" :: "r"(bar), "r"(parity) : "memory");
}
__device__ __forceinline__ void mbar_wait_soft(uint32_t bar, uint32_t parity) {
  asm volatile("{\n.reg .pred p;\n.reg .b32 c;\nmov.b32 c, 0;\nLAB_WAIT:\nmbarrier.try_wait.parity.shared::cta.b64 p, [%0], %1;\n@p bra DONE;\n"
               "add.u32 c, c, 1;\nsetp.lt.u32 p, c, 0x1000;\n@p bra LAB_WAIT;\nDONE:\n}" :: "r"(bar), "r"(parity) : "memory");
}
__device__ __forceinline__ void tma3d(uint32_t dst, const CUtensorMap* m, uint32_t bar, int c0, int c1, int c2) {
  asm volatile("cp.async.bulk.tensor.3d.shared::cluster.global.mbarrier::complete_tx::bytes [%0], [%1, {%3, %4, %5}], [%2];"
    :: "r"(dst), "l"(m), "r"(bar), "r"(c0), "r"(c1), "r"(c2) : "memory");
}
__device__ __forceinline__ void tma3d_store(const CUtensorMap* m, uint32_t src, int c0, int c1, int c2) {
  asm volatile("cp.async.bulk.tensor.3d.global.shared::cta.bulk_group [%0, {%2, %3, %4}], [%1];"
    :: "l"(m), "r"(src), "r"(c0), "r"(c1), "r"(c2) : "memory");
}
__device__ __forceinline__ void bulk_load(uint32_t dst, const void* src, uint32_t bytes, uint32_t bar) {
  asm volatile("cp.async.bulk.shared::cluster.global.mbarrier::complete_tx::bytes [%0], [%1], %2, [%3];" :: "r"(dst), "l"(src), "r"(bytes), "r"(bar) : "memory");
}
__device__ __forceinline__ void bulk_store(void* dst, uint32_t src, uint32_t bytes) {
  asm volatile("cp.async.bulk.global.shared::cta.bulk_group [%0], [%1], %2;" :: "l"(dst), "r"(src), "r"(bytes) : "memory");
}
__device__ __forceinline__ void bulk_prefetch(const void* src, uint32_t bytes) { asm volatile("cp.async.bulk.prefetch.L2.global [%0], %1;" :: "l"(src), "r"(bytes) : "memory"); }
__device__ __forceinline__ void bulk_commit_wait() { asm volatile("cp.async.bulk.commit_group;\ncp.async.bulk.wait_group 0;" ::: "memory"); }
__device__ __forceinline__ void fence_async_smem() { asm volatile("fence.proxy.async.shared::cta;" ::: "memory"); }
__device__ __forceinline__ void fence_async_global() { asm volatile("fence.proxy.async.global;" ::: "memory"); }
__device__ __forceinline__ void flag_set(uint32_t* p, uint32_t v) { asm volatile("st.release.gpu.global.u32 [%0], %1;" :: "l"(p), "r"(v) : "memory"); }
__device__ __forceinline__ uint32_t flag_get(const uint32_t* p) { uint32_t v; asm volatile("ld.acquire.gpu.global.u32 %0, [%1];" : "=r"(v) : "l"(p) : "memory"); return v; }
__device__ __forceinline__ uint32_t flag_peek(const uint32_t* p) { uint32_t v; asm volatile("ld.relaxed.gpu.global.u32 %0, [%1];" : "=r"(v) : "l"(p) : "memory"); return v; }
__device__ __forceinline__ void ll_st4(uint4* p, float a, float b, uint32_t tag) {
  asm volatile("st.relaxed.gpu.global.v2.b64 [%0], {%1, %2};" :: "l"(p),
    "l"(((uint64_t)tag << 32) | __float_as_uint(a)), "l"(((uint64_t)tag << 32) | __float_as_uint(b)) : "memory");
}
__device__ __forceinline__ bool ll_ld4(const uint4* p, float& a, float& b, uint32_t tag) {
  uint64_t x, y;
  asm volatile("ld.relaxed.gpu.global.v2.b64 {%0, %1}, [%2];" : "=l"(x), "=l"(y) : "l"(p) : "memory");
  a = __uint_as_float((uint32_t)x); b = __uint_as_float((uint32_t)y);
  return ((uint32_t)(x >> 32) == tag) & ((uint32_t)(y >> 32) == tag);
}
__device__ __forceinline__ void ll_st2(uint2* p, uint32_t a, uint32_t tag) {
  asm volatile("st.relaxed.gpu.global.b64 [%0], %1;" :: "l"(p), "l"(((uint64_t)tag << 32) | a) : "memory");
}
__device__ __forceinline__ bool ll_ld2(const uint2* p, uint32_t& a, uint32_t tag) {
  uint64_t x;
  asm volatile("ld.relaxed.gpu.global.b64 %0, [%1];" : "=l"(x) : "l"(p) : "memory");
  a = (uint32_t)x;
  return (uint32_t)(x >> 32) == tag;
}
__device__ __forceinline__ void bar_sync(int id, int n) { asm volatile("bar.sync %0, %1;" :: "r"(id), "r"(n) : "memory"); }
__device__ __forceinline__ void bar_arrive(int id, int n) { asm volatile("bar.arrive %0, %1;" :: "r"(id), "r"(n) : "memory"); }
__device__ __forceinline__ void wg_fence() { asm volatile("wgmma.fence.sync.aligned;" ::: "memory"); }
__device__ __forceinline__ void wg_commit() { asm volatile("wgmma.commit_group.sync.aligned;" ::: "memory"); }
template <int N> __device__ __forceinline__ void wg_wait() { asm volatile("wgmma.wait_group.sync.aligned %0;" :: "n"(N) : "memory"); }
__device__ __forceinline__ void stsm4(uint32_t a, uint32_t r0, uint32_t r1, uint32_t r2, uint32_t r3) {
  asm volatile("stmatrix.sync.aligned.m8n8.x4.shared.b16 [%0], {%1, %2, %3, %4};" :: "r"(a), "r"(r0), "r"(r1), "r"(r2), "r"(r3) : "memory");
}
__device__ __forceinline__ void ldsm4(uint32_t a, uint32_t (&r)[4]) {
  asm volatile("ldmatrix.sync.aligned.m8n8.x4.shared.b16 {%0, %1, %2, %3}, [%4];" : "=r"(r[0]), "=r"(r[1]), "=r"(r[2]), "=r"(r[3]) : "r"(a) : "memory");
}
__device__ __forceinline__ void ldsm4t(uint32_t a, uint32_t (&r)[4]) {
  asm volatile("ldmatrix.sync.aligned.m8n8.x4.trans.shared.b16 {%0, %1, %2, %3}, [%4];" : "=r"(r[0]), "=r"(r[1]), "=r"(r[2]), "=r"(r[3]) : "r"(a) : "memory");
}
__device__ __forceinline__ void mma16816(float (&d)[4], uint32_t a0, uint32_t a1, uint32_t a2, uint32_t a3, uint32_t b0, uint32_t b1) {
  asm volatile("mma.sync.aligned.m16n8k16.row.col.f32.bf16.bf16.f32 {%0, %1, %2, %3}, {%4, %5, %6, %7}, {%8, %9}, {%0, %1, %2, %3};"
    : "+f"(d[0]), "+f"(d[1]), "+f"(d[2]), "+f"(d[3]) : "r"(a0), "r"(a1), "r"(a2), "r"(a3), "r"(b0), "r"(b1));
}
__device__ __forceinline__ void mma1688(float (&d)[4], uint32_t a0, uint32_t a1, uint32_t b0) {
  asm volatile("mma.sync.aligned.m16n8k8.row.col.f32.bf16.bf16.f32 {%0, %1, %2, %3}, {%4, %5}, {%6}, {%0, %1, %2, %3};"
    : "+f"(d[0]), "+f"(d[1]), "+f"(d[2]), "+f"(d[3]) : "r"(a0), "r"(a1), "r"(b0));
}
__device__ __forceinline__ uint32_t pack2(float lo, float hi) { uint32_t r; asm("cvt.rn.bf16x2.f32 %0, %1, %2;" : "=r"(r) : "f"(hi), "f"(lo)); return r; }
__device__ __forceinline__ uint32_t pack2_relu(float lo, float hi) { uint32_t r; asm("cvt.rn.relu.bf16x2.f32 %0, %1, %2;" : "=r"(r) : "f"(hi), "f"(lo)); return r; }
__device__ __forceinline__ float bf_lo(uint32_t v) { return __uint_as_float(v << 16); }
__device__ __forceinline__ float bf_hi(uint32_t v) { return __uint_as_float(v & 0xffff0000u); }
__device__ __forceinline__ float lds_f(uint32_t a) { float v; asm volatile("ld.shared.f32 %0, [%1];" : "=f"(v) : "r"(a) : "memory"); return v; }
__device__ __forceinline__ float2 lds_f2(uint32_t a) { float2 v; asm volatile("ld.shared.v2.f32 {%0, %1}, [%2];" : "=f"(v.x), "=f"(v.y) : "r"(a) : "memory"); return v; }
__device__ __forceinline__ uint32_t lds_u(uint32_t a) { uint32_t v; asm volatile("ld.shared.u32 %0, [%1];" : "=r"(v) : "r"(a) : "memory"); return v; }
__device__ __forceinline__ uint4 lds_u4(uint32_t a) { uint4 v; asm volatile("ld.shared.v4.u32 {%0, %1, %2, %3}, [%4];" : "=r"(v.x), "=r"(v.y), "=r"(v.z), "=r"(v.w) : "r"(a) : "memory"); return v; }
__device__ __forceinline__ uint2 lds_u2(uint32_t a) { uint2 v; asm volatile("ld.shared.v2.u32 {%0, %1}, [%2];" : "=r"(v.x), "=r"(v.y) : "r"(a) : "memory"); return v; }
__device__ __forceinline__ void sts_u2(uint32_t a, uint32_t x, uint32_t y) { asm volatile("st.shared.v2.u32 [%0], {%1, %2};" :: "r"(a), "r"(x), "r"(y) : "memory"); }
__device__ __forceinline__ void sts_f(uint32_t a, float v) { asm volatile("st.shared.f32 [%0], %1;" :: "r"(a), "f"(v) : "memory"); }
__device__ __forceinline__ void sts_f2(uint32_t a, float x, float y) { asm volatile("st.shared.v2.f32 [%0], {%1, %2};" :: "r"(a), "f"(x), "f"(y) : "memory"); }
__device__ __forceinline__ float4 lds_f4(uint32_t a) { float4 v; asm volatile("ld.shared.v4.f32 {%0, %1, %2, %3}, [%4];" : "=f"(v.x), "=f"(v.y), "=f"(v.z), "=f"(v.w) : "r"(a) : "memory"); return v; }
__device__ __forceinline__ float rcp(float x) { float y; asm("rcp.approx.ftz.f32 %0, %1;" : "=f"(y) : "f"(x)); return y; }
__device__ __forceinline__ float ex2(float x) { float y; asm("ex2.approx.ftz.f32 %0, %1;" : "=f"(y) : "f"(x)); return y; }

__device__ __forceinline__ void wgmma_n128(float (&d)[64], uint32_t da, uint32_t db, int scale_d) {
  asm volatile("{\n.reg .pred p;\n.reg .b64 a, b;\n.reg .b32 h;\nmov.b32 h, 0x40000040;\nmov.b64 a, {%64, h};\nmov.b64 b, {%65, h};\nsetp.ne.b32 p, %66, 0;\n"
    "wgmma.mma_async.sync.aligned.m64n128k16.f32.bf16.bf16 "
    "{%0, %1, %2, %3, %4, %5, %6, %7, %8, %9, %10, %11, %12, %13, %14, %15, %16, %17, %18, %19, %20, %21, %22, %23, %24, %25, %26, %27, %28, %29, %30, %31, %32, %33, %34, %35, %36, %37, %38, %39, %40, %41, %42, %43, %44, %45, %46, %47, %48, %49, %50, %51, %52, %53, %54, %55, %56, %57, %58, %59, %60, %61, %62, %63}, a, b, p, 1, 1, 0, 1;\n}\n"
    : "+f"(d[0]), "+f"(d[1]), "+f"(d[2]), "+f"(d[3]), "+f"(d[4]), "+f"(d[5]), "+f"(d[6]), "+f"(d[7]), "+f"(d[8]), "+f"(d[9]), "+f"(d[10]), "+f"(d[11]), "+f"(d[12]), "+f"(d[13]), "+f"(d[14]), "+f"(d[15]), "+f"(d[16]), "+f"(d[17]), "+f"(d[18]), "+f"(d[19]), "+f"(d[20]), "+f"(d[21]), "+f"(d[22]), "+f"(d[23]), "+f"(d[24]), "+f"(d[25]), "+f"(d[26]), "+f"(d[27]), "+f"(d[28]), "+f"(d[29]), "+f"(d[30]), "+f"(d[31]), "+f"(d[32]), "+f"(d[33]), "+f"(d[34]), "+f"(d[35]), "+f"(d[36]), "+f"(d[37]), "+f"(d[38]), "+f"(d[39]), "+f"(d[40]), "+f"(d[41]), "+f"(d[42]), "+f"(d[43]), "+f"(d[44]), "+f"(d[45]), "+f"(d[46]), "+f"(d[47]), "+f"(d[48]), "+f"(d[49]), "+f"(d[50]), "+f"(d[51]), "+f"(d[52]), "+f"(d[53]), "+f"(d[54]), "+f"(d[55]), "+f"(d[56]), "+f"(d[57]), "+f"(d[58]), "+f"(d[59]), "+f"(d[60]), "+f"(d[61]), "+f"(d[62]), "+f"(d[63])
    : "r"(da), "r"(db), "r"(scale_d));
}
__device__ __forceinline__ void wgmma_n192(float (&d)[96], uint32_t da, uint32_t db, int scale_d) {
  asm volatile("{\n.reg .pred p;\n.reg .b64 a, b;\n.reg .b32 h;\nmov.b32 h, 0x40000040;\nmov.b64 a, {%96, h};\nmov.b64 b, {%97, h};\nsetp.ne.b32 p, %98, 0;\n"
    "wgmma.mma_async.sync.aligned.m64n192k16.f32.bf16.bf16 "
    "{%0, %1, %2, %3, %4, %5, %6, %7, %8, %9, %10, %11, %12, %13, %14, %15, %16, %17, %18, %19, %20, %21, %22, %23, %24, %25, %26, %27, %28, %29, %30, %31, %32, %33, %34, %35, %36, %37, %38, %39, %40, %41, %42, %43, %44, %45, %46, %47, %48, %49, %50, %51, %52, %53, %54, %55, %56, %57, %58, %59, %60, %61, %62, %63, %64, %65, %66, %67, %68, %69, %70, %71, %72, %73, %74, %75, %76, %77, %78, %79, %80, %81, %82, %83, %84, %85, %86, %87, %88, %89, %90, %91, %92, %93, %94, %95}, a, b, p, 1, 1, 0, 1;\n}\n"
    : "+f"(d[0]), "+f"(d[1]), "+f"(d[2]), "+f"(d[3]), "+f"(d[4]), "+f"(d[5]), "+f"(d[6]), "+f"(d[7]), "+f"(d[8]), "+f"(d[9]), "+f"(d[10]), "+f"(d[11]), "+f"(d[12]), "+f"(d[13]), "+f"(d[14]), "+f"(d[15]), "+f"(d[16]), "+f"(d[17]), "+f"(d[18]), "+f"(d[19]), "+f"(d[20]), "+f"(d[21]), "+f"(d[22]), "+f"(d[23]), "+f"(d[24]), "+f"(d[25]), "+f"(d[26]), "+f"(d[27]), "+f"(d[28]), "+f"(d[29]), "+f"(d[30]), "+f"(d[31]), "+f"(d[32]), "+f"(d[33]), "+f"(d[34]), "+f"(d[35]), "+f"(d[36]), "+f"(d[37]), "+f"(d[38]), "+f"(d[39]), "+f"(d[40]), "+f"(d[41]), "+f"(d[42]), "+f"(d[43]), "+f"(d[44]), "+f"(d[45]), "+f"(d[46]), "+f"(d[47]), "+f"(d[48]), "+f"(d[49]), "+f"(d[50]), "+f"(d[51]), "+f"(d[52]), "+f"(d[53]), "+f"(d[54]), "+f"(d[55]), "+f"(d[56]), "+f"(d[57]), "+f"(d[58]), "+f"(d[59]), "+f"(d[60]), "+f"(d[61]), "+f"(d[62]), "+f"(d[63]), "+f"(d[64]), "+f"(d[65]), "+f"(d[66]), "+f"(d[67]), "+f"(d[68]), "+f"(d[69]), "+f"(d[70]), "+f"(d[71]), "+f"(d[72]), "+f"(d[73]), "+f"(d[74]), "+f"(d[75]), "+f"(d[76]), "+f"(d[77]), "+f"(d[78]), "+f"(d[79]), "+f"(d[80]), "+f"(d[81]), "+f"(d[82]), "+f"(d[83]), "+f"(d[84]), "+f"(d[85]), "+f"(d[86]), "+f"(d[87]), "+f"(d[88]), "+f"(d[89]), "+f"(d[90]), "+f"(d[91]), "+f"(d[92]), "+f"(d[93]), "+f"(d[94]), "+f"(d[95])
    : "r"(da), "r"(db), "r"(scale_d));
}
__device__ __forceinline__ void wgmma_n256(float (&d)[128], uint32_t da, uint32_t db, int scale_d) {
  asm volatile("{\n.reg .pred p;\n.reg .b64 a, b;\n.reg .b32 h;\nmov.b32 h, 0x40000040;\nmov.b64 a, {%128, h};\nmov.b64 b, {%129, h};\nsetp.ne.b32 p, %130, 0;\n"
    "wgmma.mma_async.sync.aligned.m64n256k16.f32.bf16.bf16 "
    "{%0, %1, %2, %3, %4, %5, %6, %7, %8, %9, %10, %11, %12, %13, %14, %15, %16, %17, %18, %19, %20, %21, %22, %23, %24, %25, %26, %27, %28, %29, %30, %31, %32, %33, %34, %35, %36, %37, %38, %39, %40, %41, %42, %43, %44, %45, %46, %47, %48, %49, %50, %51, %52, %53, %54, %55, %56, %57, %58, %59, %60, %61, %62, %63, %64, %65, %66, %67, %68, %69, %70, %71, %72, %73, %74, %75, %76, %77, %78, %79, %80, %81, %82, %83, %84, %85, %86, %87, %88, %89, %90, %91, %92, %93, %94, %95, %96, %97, %98, %99, %100, %101, %102, %103, %104, %105, %106, %107, %108, %109, %110, %111, %112, %113, %114, %115, %116, %117, %118, %119, %120, %121, %122, %123, %124, %125, %126, %127}, a, b, p, 1, 1, 0, 1;\n}\n"
    : "+f"(d[0]), "+f"(d[1]), "+f"(d[2]), "+f"(d[3]), "+f"(d[4]), "+f"(d[5]), "+f"(d[6]), "+f"(d[7]), "+f"(d[8]), "+f"(d[9]), "+f"(d[10]), "+f"(d[11]), "+f"(d[12]), "+f"(d[13]), "+f"(d[14]), "+f"(d[15]), "+f"(d[16]), "+f"(d[17]), "+f"(d[18]), "+f"(d[19]), "+f"(d[20]), "+f"(d[21]), "+f"(d[22]), "+f"(d[23]), "+f"(d[24]), "+f"(d[25]), "+f"(d[26]), "+f"(d[27]), "+f"(d[28]), "+f"(d[29]), "+f"(d[30]), "+f"(d[31]), "+f"(d[32]), "+f"(d[33]), "+f"(d[34]), "+f"(d[35]), "+f"(d[36]), "+f"(d[37]), "+f"(d[38]), "+f"(d[39]), "+f"(d[40]), "+f"(d[41]), "+f"(d[42]), "+f"(d[43]), "+f"(d[44]), "+f"(d[45]), "+f"(d[46]), "+f"(d[47]), "+f"(d[48]), "+f"(d[49]), "+f"(d[50]), "+f"(d[51]), "+f"(d[52]), "+f"(d[53]), "+f"(d[54]), "+f"(d[55]), "+f"(d[56]), "+f"(d[57]), "+f"(d[58]), "+f"(d[59]), "+f"(d[60]), "+f"(d[61]), "+f"(d[62]), "+f"(d[63]), "+f"(d[64]), "+f"(d[65]), "+f"(d[66]), "+f"(d[67]), "+f"(d[68]), "+f"(d[69]), "+f"(d[70]), "+f"(d[71]), "+f"(d[72]), "+f"(d[73]), "+f"(d[74]), "+f"(d[75]), "+f"(d[76]), "+f"(d[77]), "+f"(d[78]), "+f"(d[79]), "+f"(d[80]), "+f"(d[81]), "+f"(d[82]), "+f"(d[83]), "+f"(d[84]), "+f"(d[85]), "+f"(d[86]), "+f"(d[87]), "+f"(d[88]), "+f"(d[89]), "+f"(d[90]), "+f"(d[91]), "+f"(d[92]), "+f"(d[93]), "+f"(d[94]), "+f"(d[95]), "+f"(d[96]), "+f"(d[97]), "+f"(d[98]), "+f"(d[99]), "+f"(d[100]), "+f"(d[101]), "+f"(d[102]), "+f"(d[103]), "+f"(d[104]), "+f"(d[105]), "+f"(d[106]), "+f"(d[107]), "+f"(d[108]), "+f"(d[109]), "+f"(d[110]), "+f"(d[111]), "+f"(d[112]), "+f"(d[113]), "+f"(d[114]), "+f"(d[115]), "+f"(d[116]), "+f"(d[117]), "+f"(d[118]), "+f"(d[119]), "+f"(d[120]), "+f"(d[121]), "+f"(d[122]), "+f"(d[123]), "+f"(d[124]), "+f"(d[125]), "+f"(d[126]), "+f"(d[127])
    : "r"(da), "r"(db), "r"(scale_d));
}

template <int NB> struct Mma;
template <> struct Mma<2> { static __device__ __forceinline__ void run(float (&d)[64], uint32_t a, uint32_t b, int s) { wgmma_n128(d, a, b, s); } };
template <> struct Mma<3> { static __device__ __forceinline__ void run(float (&d)[96], uint32_t a, uint32_t b, int s) { wgmma_n192(d, a, b, s); } };
template <> struct Mma<4> {
  static __device__ __forceinline__ void run(float (&d)[128], uint32_t a, uint32_t b, int s) {
    wgmma_n128(*reinterpret_cast<float (*)[64]>(&d[0]), a, b, s);
    wgmma_n128(*reinterpret_cast<float (*)[64]>(&d[64]), a, b + 1024, s);
  }
};

constexpr uint32_t DESC_A = 1u << 16;
constexpr uint32_t DESC_B = (8192u >> 4) << 16;

struct Params { CUtensorMap x, wqkv, wo, w1a, w1b, w2, out; uint16_t sched[144]; uint32_t ta[144], tb[144]; };

struct Ptrs { const bf16* in[4]; uint32_t* epoch; };

template <int NB, bool QKV = false>
__device__ __forceinline__ void mainloop(float (&acc)[NB * 32], const Params& P, uint32_t sb, uint32_t sb2, int wg, int i0, int nsteps, int slot) {
  const uint32_t a0 = DESC_A + (((sb & 0x3ffff) + wg * 8192) >> 4), b0 = DESC_B + ((sb & 0x3ffff) >> 4);
  {
    const uint32_t e = QKV && i0 == 0 ? 96 + 33 * HEAD0 : P.sched[i0];
    const uint32_t da = a0 + ((e & 0x3e0) << 4), db = b0 + ((e & 31) << 9);
    if ((threadIdx.x & 127) == 0) TRACE(3 + wg, i0);
    mbar_wait(sb + BAR_FULL, 0);
    if (threadIdx.x == 0) TRACE(2, i0);
    wg_fence();
#pragma unroll
    for (int kk = 0; kk < 4; kk++) Mma<NB>::run(acc, da + kk * 2, db + kk * 128, kk > 0);
    wg_commit();
  }
#pragma unroll 1
  for (int i = i0 + 1; i < i0 + nsteps; i++) {
    const uint32_t e = P.sched[i];
    const uint32_t da = a0 + ((e & 0x3e0) << 4), db = b0 + ((e & 31) << 9);
    if ((threadIdx.x & 127) == 0) TRACE(3 + wg, i);
    mbar_wait(sb + BAR_FULL + (i & 7) * 8, (i >> 3) & 1);
    if (threadIdx.x == 0) TRACE(2, i);
    wg_fence();
#pragma unroll
    for (int kk = 0; kk < 4; kk++) Mma<NB>::run(acc, da + kk * 2, db + kk * 128, 1);
    wg_commit();
    wg_wait<1>();
    release_elect(sb + BAR_EMPTY + ((i - 1) & 7) * 8, sb2 + BAR_EMPTY + ((i - 1) & 7) * 8);
  }
}
template <bool BB, int N>
__device__ __forceinline__ void mainloop_end(float (&acc)[N], uint32_t sb, uint32_t sb2, uint32_t bar, uint32_t parity) {
  wg_wait<0>();
#pragma unroll
  for (int j = 0; j < N; j++) asm volatile("" : "+f"(acc[j]) :: "memory");
  release_elect(sb + BAR_EMPTY + 56, sb2 + BAR_EMPTY + 56);
  if (BB) mbar_wait(bar, parity);
}

__device__ __forceinline__ uint4 ldg_u4(const void* p) {
  uint4 v;
  asm volatile("ld.global.nc.L1::no_allocate.v4.u32 {%0, %1, %2, %3}, [%4];" : "=r"(v.x), "=r"(v.y), "=r"(v.z), "=r"(v.w) : "l"(p));
  return v;
}
__device__ __forceinline__ float2 colsum_fold(const float (&cs)[8], int lane) {
  const bool u = lane & 16, z = lane & 8;
  float t[4];
#pragma unroll
  for (int q = 0; q < 4; q++) t[q] = (u ? cs[4 + q] : cs[q]) + __shfl_xor_sync(0xffffffffu, u ? cs[q] : cs[4 + q], 16);
  return make_float2((z ? t[2] : t[0]) + __shfl_xor_sync(0xffffffffu, z ? t[0] : t[2], 8), (z ? t[3] : t[1]) + __shfl_xor_sync(0xffffffffu, z ? t[1] : t[3], 8));
}
__device__ __forceinline__ float2 colsum64(const bf16* w, int ld, int lane) {
  const bf16* p = w + (lane >> 3) * ld + (lane & 7) * 8;
  uint4 v[16];
#pragma unroll
  for (int q = 0; q < 16; q++) v[q] = ldg_u4(p + q * 4 * ld);
  float cs[8] = {bf_lo(v[0].x), bf_hi(v[0].x), bf_lo(v[0].y), bf_hi(v[0].y), bf_lo(v[0].z), bf_hi(v[0].z), bf_lo(v[0].w), bf_hi(v[0].w)};
#pragma unroll
  for (int q = 1; q < 16; q++) {
    cs[0] += bf_lo(v[q].x); cs[1] += bf_hi(v[q].x); cs[2] += bf_lo(v[q].y); cs[3] += bf_hi(v[q].y);
    cs[4] += bf_lo(v[q].z); cs[5] += bf_hi(v[q].z); cs[6] += bf_lo(v[q].w); cs[7] += bf_hi(v[q].w);
  }
  return colsum_fold(cs, lane);
}
template <int NS>
__device__ __forceinline__ void colsum_gather(const uint4* src, uint32_t dst, int t, uint32_t tag) {
  uint32_t spin = 0;
  while (true) {
    float a = 0.f, b = 0.f;
    bool ok = true;
#pragma unroll
    for (int k = 0; k < NS; k++) { float x, y; ok &= ll_ld4(src + k * 128 + t, x, y, tag); a += x; b += y; }
    if (ok) { sts_f2(dst + (t >> 3) * 64 + (t & 3) * 16 + (t & 4) * 2, a, b); break; }
    if (++spin > SPIN_LIMIT) __trap();
    __nanosleep(200);
  }
  __syncwarp();
}
__device__ __forceinline__ uint32_t get_tag(const uint32_t* epoch) { return *(const volatile uint32_t*)epoch + 1; }
__device__ __forceinline__ void mom8(const uint4& v, float (&s)[4]) {
  const uint32_t u[4] = {v.x, v.y, v.z, v.w};
#pragma unroll
  for (int z = 0; z < 4; z++) { const float a = bf_lo(u[z]), b = bf_hi(u[z]); s[0] += a; s[1] += b; s[2] = fmaf(a, a, s[2]); s[3] = fmaf(b, b, s[3]); }
}
__device__ __forceinline__ void sq8(uint4 v, float mean, float& m) {
  asm volatile("" : "+r"(v.x), "+r"(v.y), "+r"(v.z), "+r"(v.w));
  const uint32_t u[4] = {v.x, v.y, v.z, v.w};
#pragma unroll
  for (int z = 0; z < 4; z++) { const float a = bf_lo(u[z]) - mean, b = bf_hi(u[z]) - mean; m = fmaf(a, a, fmaf(b, b, m)); }
}

__device__ __forceinline__ uint32_t others(int c) {
  return (0x103210u + ((c & 4) ^ 4) * 0x1111u) | (((c ^ 2) & 6) * 0x110000u);
}
__device__ __forceinline__ void wait_flags(const uint32_t* flag, uint32_t tag, uint32_t& ready, uint32_t need) {
  if ((ready & need) != need) {
    uint32_t spin = 0;
    do {
      ready = __ballot_sync(0xffffffffu, flag_get(flag) == tag);
      if (++spin > SPIN_LIMIT) __trap();
    } while ((ready & need) != need);
    fence_async_global();
  }
}

__global__ void __cluster_dims__(2, 1, 1) __launch_bounds__(512, 1)
fused_block_kernel(const __grid_constant__ Ptrs G, const __grid_constant__ Params P) {
  extern __shared__ __align__(1024) uint8_t smem[];
  uint32_t sb = (uint32_t)__cvta_generic_to_shared(smem);
  const int tid = threadIdx.x, lane = tid & 31, warp = __shfl_sync(0xffffffffu, tid >> 5, 0);

  const bf16* pf = G.in[(tid >> 6) & 1];
  asm volatile("" : "+l"(pf));
  const bf16 *x = G.in[0], *wqkv = G.in[1], *wo = G.in[2], *w2 = G.in[3];

  int slot = blockIdx.x;
  {
    uint32_t smid, nsmid;
    asm volatile("mov.u32 %0, %%smid;" : "=r"(smid));
    asm volatile("mov.u32 %0, %%nsmid;" : "=r"(nsmid));
    if (nsmid == 132) {
      const int t = smid >> 1;
      int g, p;
      if (t < 32) { g = t & 7; p = t >> 3; }
      else if (t < 60) { g = 1 + (t - 32) % 7; p = 4 + (t - 32) / 7; }
      else { g = 0; p = t - 58; }
      slot = ((g & 3) * 4 + (p >> 1)) * 8 + (g >> 2) * 4 + (p & 1) * 2 + (smid & 1);
      if (t == 60 || t == 61) slot = 128 + (smid - 120);
    }
  }
  if (tid == 0) { PROFG(0); PROF(1); }
  if (slot >= 128) {
    if (tid == 0) {
      for (int s = 0; s < 6; s++) { mbar_init(sb + BAR_FULL + s * 8, 1); mbar_init(sb + BAR_EMPTY + s * 8, 8); }
      mbar_init(sb + BAR_ID, slot + 1);
      asm volatile("fence.mbarrier_init.release.cluster;" ::: "memory");
      fence_async_smem();
    }
    __syncthreads();
    asm volatile("barrier.cluster.arrive.relaxed.aligned;" ::: "memory");
    const uint32_t tag = get_tag(G.epoch + slot);
    uint32_t st = 0, ph = 0;
    if (warp == 8) {
#pragma unroll 1
      for (int job = 0; job < 6; job++) {
        const int j = job >> 1, cc = (slot - 128) * 2 + (job & 1);
        const CUtensorMap* map = j == 0 ? &P.wqkv : j == 1 ? &P.w1a : &P.w1b;
        const int c0 = j == 0 ? (8 + cc) * 64 : 0, c2 = j == 0 ? 0 : j == 1 ? 4 * cc : 32 + 3 * cc;
#pragma unroll 1
        for (int k = 0; k < 16; k++) {
          mbar_wait(sb + BAR_EMPTY + st * 8, ph ^ 1);
          issue_tma3d(sb + st * 32768, map, sb + BAR_FULL + st * 8, j == 1 ? 4 * UNIT : 3 * UNIT, c0, k * 64, c2);
          if (++st == 6) { st = 0; ph ^= 1; }
        }
      }
    } else if (warp < 8) {
      const int row = warp * 4 + (lane >> 3);
      const uint32_t off = sb + row * 128 + (((lane ^ row) & 7) << 4);
#pragma unroll 1
      for (int job = 0; job < 6; job++) {
        const int n = (job >> 1) == 1 ? 4 : 3;
        float cs[4][8];
#pragma unroll
        for (int q = 0; q < 32; q++) cs[q >> 3][q & 7] = 0.f;
#pragma unroll 1
        for (int k = 0; k < 16; k++) {
          mbar_wait(sb + BAR_FULL + st * 8, ph);
          uint4 v[8];
#pragma unroll
          for (int q = 0; q < 8; q++) v[q] = lds_u4(off + st * 32768 + q * 4096);
          arrive_elect(sb + BAR_EMPTY + st * 8, 1);
#pragma unroll
          for (int q = 0; q < 8; q++) {
            float* a = cs[q >> 1];
            a[0] += bf_lo(v[q].x); a[1] += bf_hi(v[q].x); a[2] += bf_lo(v[q].y); a[3] += bf_hi(v[q].y);
            a[4] += bf_lo(v[q].z); a[5] += bf_hi(v[q].z); a[6] += bf_lo(v[q].w); a[7] += bf_hi(v[q].w);
          }
          if (++st == 6) { st = 0; ph ^= 1; }
        }
        const uint32_t red = sb + 196608 + (job & 1) * 8192;
#pragma unroll
        for (int q = 0; q < 4; q++) { const float2 y = colsum_fold(cs[q], lane); sts_f2(red + q * 2048 + warp * 256 + ((lane & 7) * 4 + (lane >> 3)) * 8, y.x, y.y); }
        bar_sync(1, 256);
        if (warp < n) {
          float a = 0.f, b = 0.f;
#pragma unroll
          for (int q = 0; q < 8; q++) { const float2 y = lds_f2(red + warp * 2048 + q * 256 + lane * 8); a += y.x; b += y.y; }
          ll_st4(&g_cs2[((job >> 1) * 8 + (slot - 128) * 2 + (job & 1)) * 128 + warp * 32 + lane], a, b, tag);
        }
        if (tid == 0) PROF(40 + (job >> 1));
      }
    }
    if (tid < 128) {
      float a, b; uint32_t spin = 0;
      while (!ll_ld4(&g_stats[tid * 16], a, b, tag)) { if (++spin > SPIN_LIMIT) __trap(); __nanosleep(200); }
    }
    __syncthreads();
    if (tid == 0) G.epoch[slot] = tag;
    return;
  }
  const int r = slot >> 3, c = slot & 7;
  const int par = r >> 3, s2base = (r & 7) * 128;

  if (tid == 0) {
    for (int s = 0; s < 4; s++) mbar_init(sb + BAR_FULL + s * 8, 2);
    asm volatile("fence.mbarrier_init.release.cluster;" ::: "memory");
    fence_async_smem();
#pragma unroll
    for (int i = 0; i < 4; i++) {
      TRACE(0, i); TRACE(1, i);
      mbar_expect_tx(sb + BAR_FULL + i * 8, 5 * UNIT);
      tma3d(sb + ((HEAD0 + i * 5) % 20 + 3) * UNIT, &P.x, sb + BAR_FULL + i * 8, i * 64, par, s2base);
      tma3d(sb + (HEAD0 + i * 5) % 20 * UNIT, &P.wqkv, sb + BAR_FULL + i * 8, c * 64, i * 64, 0);
      mbar_arrive(sb + BAR_FULL + i * 8);
    }
  }
  if (tid == 352) {
    if (sb & 1023) __trap();
    for (int s = 0; s < 8; s++) { if (s >= 4) mbar_init(sb + BAR_FULL + s * 8, 2); mbar_init(sb + BAR_EMPTY + s * 8, 16); }
    mbar_init(sb + BAR_OATT, 8); mbar_init(sb + BAR_E2C, 4);
    for (int w = 0; w < 2; w++) {
      mbar_init(sb + BAR_ID + w * 8, (slot ^ w) + 1); mbar_init(sb + BAR_DUMPH + w * 8, 4); mbar_init(sb + BAR_DUMPS + w * 8, 4);
      mbar_init(sb + BAR_SFREE + w * 8, 1); mbar_init(sb + BAR_RESH + w * 8, 1);
    }
    mbar_init(sb + BAR_RESX, 1); mbar_init(sb + BAR_O2, 1); mbar_init(sb + BAR_OFREE, 1); mbar_init(sb + BAR_QKV, 1);
    asm volatile("fence.mbarrier_init.release.cluster;" ::: "memory");
    fence_async_smem();
  }
  __syncthreads();
  asm volatile("barrier.cluster.arrive.relaxed.aligned;" ::: "memory");
  if (tid == 0) PROF(43);

  if (warp >= 12) {
    asm volatile("setmaxnreg.dec.sync.aligned.u32 40;");
    if (warp == 12) {
      if (S5 == 1) mbar_wait(sb + BAR_FULL, 0);
#pragma unroll 1
      for (int i = 4; i < 32; i++) {
        step_tma(sb, P.ta[i], &P.x, 16384, (i & 15) * 64, par, s2base);
        if (lane == 0) TRACE(0, i);
      }
      const bool paired = is_paired(sb);
      const uint32_t tag = lds_u(sb + OFF_TAG);
      const uint32_t* flag = g_flags + r * 96 + lane;
      const uint8_t* base = g_H + r * (56 * 16384);
      uint32_t ready = 0;
      int i = 32;
#pragma unroll 1
      for (int m = 0; m < 4; m++) {
        const uint8_t* src = base;
        int end = 40;
        uint32_t need = 0xffu;
        if (m == 1) { end = 80; need = 0xffffffffu; }
        if (m >= 2) { src = g_H + (r * 56 + (m - 2) * 32) * 16384; end = m == 2 ? 112 - 2 * EP : 136; need = 0xffffu << ((m - 2) * 16); }
        if (m == 2) { flag += 32; ready = 0; }
        if (m >= 2) {
          uint32_t* sy = g_sync + (((r >> 2) * 2 + (c >> 2)) * 4 + m) * 32;
          if (((SY >> m) & 1) && lane == 0) *(volatile uint32_t*)(sy + (r & 3) * 4 + (c & 3)) = tag;
          uint32_t u = ((SY >> m) & 1) ? flag_peek(sy + (lane & 15)) : tag, v = flag_peek(flag), spin = 0;
          if (EP && m == 3) { step_bulk(sb, P.ta[110], 0, src - 32768, 16384); step_bulk(sb, P.ta[111], 0, src - 16384, 16384); i = 112; }
          while (((SY >> m) & 1) && !__all_sync(0xffffffffu, u == tag)) {
            u = flag_peek(sy + (lane & 15)); v = flag_peek(flag);
            if (++spin > SPIN_LIMIT) __trap();
          }
          ready = __ballot_sync(0xffffffffu, v == tag);
          fence_async_global();
        }
        wait_flags(flag, tag, ready, need);
#pragma unroll 1
        for (; i < end; i++, src += 16384) {
          step_bulk(sb, P.ta[i], 0, src, 16384);
          if (lane == 0) TRACE(0, i);
        }
        if (m) continue;
#pragma unroll 1
        for (int q = 0; q < 3; q++) {
          uint32_t kw = others(c), skip = 0, pat = 0x10001u << (q >> 1), sh = 1;
          if (q == 0) {
            base += 8 * 16384; pat = 0x100; sh = 0;
            if (r & 7) skip = 1024;
            if (paired) { step_arm(sb, P.ta[41], 16384); peer_push(sb + (P.ta[41] & 0x3e000) + skip, sb + OFF_S + skip, 16384 - skip, sb + BAR_FULL + 8); }
            else { wait_flags(flag, tag, ready, 0x100 << (c ^ 1)); step_bulk(sb, P.ta[41], skip, base + (c ^ 1) * 16384 + skip, 16384 - skip); }
            i = 42;
          } else if (q == 1) {
            wait_flags(flag, tag, ready, 0x100 << c);
            base = g_h + r * (16 * 16384); flag += 32; ready = 0;
            step_arm(sb, P.ta[48], 0); step_arm(sb, P.ta[49], 0);
#pragma unroll 1
            for (int z = 0; z < 2; z++) {
              const uint32_t t = P.ta[50 + z];
              if (paired) {
                step_arm(sb, t, 16384);
                mbar_wait(sb + BAR_DUMPS, 0); mbar_wait(sb + BAR_DUMPS + 8, 0);
                peer_push(sb + (t & 0x3e000), sb + OFF_S + 16384 + z * 16384, 16384, sb + BAR_FULL + 16 + z * 8);
              } else {
                wait_flags(flag, tag, ready, 0x10001 << (2 * (c ^ 1) + z));
                step_bulk(sb, t, 0, base + (c ^ 1) * 32768 + z * 16384, 16384);
              }
            }
            i = 52;
          }
          src = base + skip + (q >> 1) * 16384;
#pragma unroll 1
          for (end = i + 6; i < end; i++, kw >>= 4) {
            const uint32_t kb = (kw & 7) << sh;
            wait_flags(flag, tag, ready, pat << kb);
            step_bulk(sb, P.ta[i], skip, src + kb * 16384, 16384 - skip);
            if (lane == 0) TRACE(0, i);
          }
        }
      }
      mbar_wait(sb + BAR_EMPTY + 56, 0);
    } else if (warp == 13) {
      int i = 4;
      if (S5 == 1) mbar_wait(sb + BAR_FULL, 0);
#pragma unroll 1
      for (int m = 0; m < 5; m++) {
        const CUtensorMap* map = &P.wqkv;
        uint32_t bytes = 3 * UNIT;
        int c0 = (m * 8 + c) * 64, c1 = m ? 0 : 256, c2 = 0, end = 16 + m * 16;
        if (m >= 2) { c0 = 0; c2 = 2 * c; bytes = 2 * UNIT; map = &P.wo; end = 40; }
        if (m == 3) { map = &P.w1b; c2 = 32 + 3 * c; bytes = 3 * UNIT; end = 80; }
        if (m == 4) { map = &P.w2; end = 136; }
#pragma unroll 1
        for (; i < end; i++, c1 += 64) {
          step_tma(sb, P.tb[i], map, bytes, c0, c1, c2);
          if (lane == 0) TRACE(1, i);
        }
        if (m != 2) continue;
        const uint32_t oth = others(c);
#pragma unroll 1
        for (int q = 0; q < 3; q++) {
          uint32_t kw = (c | ((c ^ 1) << 4) | (oth << 8)) + 0x88888888u;
          if (q) { map = &P.w1a; c2 = 4 * c; bytes = 4 * UNIT; kw = (0x10 + 0x22 * c) | ((0x10 + 0x22 * (c ^ 1)) << 8) | (oth << 17); }
          if (q == 2) kw = ((oth >> 15) & 0xee) | (oth << 9) | 0x11111100u;
#pragma unroll 1
          for (end = i + 8; i < end; i++, kw >>= 4) {
            step_tma(sb, P.tb[i], map, bytes, 0, (kw & 15) * 64, c2);
            if (lane == 0) TRACE(1, i);
          }
        }
      }
    } else if (lane == 0) {
      const int w = warp - 14;
      const uint32_t tag = get_tag(G.epoch + slot);
      const uint32_t s0 = sb + OFF_S + w * 8192;
      uint32_t* flags = g_flags + r * 96;
      {
#pragma unroll
        for (int j = 0; j < 3; j++) asm volatile("prefetch.tensormap [%0];" :: "l"(&P.wqkv + w * 3 + j) : "memory");
        uint32_t z = 1;
#pragma unroll
        for (int j = 16; j < 144; j += 16) z &= (w ? P.ta[j] : P.tb[j]) & P.sched[j];
        if (z) __trap();
      }
      if (w == 0) {
#pragma unroll 1
        for (int wave = 0; wave < 2; wave++) {
          uint8_t* dst = g_H + (r * 56 + wave * 8 + c) * 16384;
          mbar_wait(sb + BAR_OATT, wave);
          if (OS >= 0 && wave == 0) mbar_wait_soft(sb + BAR_EMPTY + (OS + (c & 3)) * 8, 0);
          bulk_store(dst + 1024, s0 + 1024, 15360);
          if (wave == 0) mbar_wait(sb + BAR_O2, 0);
          if (wave == 0 || (r & 7) == 0) bulk_store(dst, s0, 1024);
          bulk_commit_wait();
          if (wave == 0) mbar_arrive(sb + BAR_OFREE);
          flag_set(flags + wave * 8 + c, tag);
          PROF(33 + wave); if (wave) PROF(45 + (c & 3));
        }
      } else {
        mbar_wait_soft(sb + BAR_FULL + 16, 0);
        mbar_wait_soft(sb + BAR_FULL + 16, 1);
#pragma unroll 1
        for (int j = 0; j < PFN; j++) {
          const int i = 18 + 2 * j;
          mbar_wait_soft(sb + BAR_FULL + (i & 7) * 8, (i >> 3) & 1);
          bulk_prefetch(j < 2 ? (const uint8_t*)wo + slot * 16384 + j * 8192 : (const uint8_t*)w2 + slot * 57344 + (j - 2) * 8192, 8192);
        }
      }
      mbar_wait(sb + BAR_DUMPH + w * 8, 0);
      bulk_store(g_h + (r * 16 + 2 * c) * 16384 + w * 8192, s0 + 16384, 8192);
      bulk_commit_wait();
      flag_set(flags + 32 + w * 16 + 2 * c, tag);
      if (w == 0) PROF(49 + (c & 3));
      mbar_wait(sb + BAR_DUMPS + w * 8, 0);
      if (H2 >= 8) mbar_wait_soft(sb + BAR_FULL + (H2 - 8 + w) * 8, 0); else mbar_wait_soft(sb + BAR_EMPTY + H2 * 8, 0);
      bulk_store(g_h + (r * 16 + 2 * c + 1) * 16384 + w * 8192, s0 + 32768, 8192);
      bulk_commit_wait();
      flag_set(flags + 32 + w * 16 + 2 * c + 1, tag);
      mbar_arrive(sb + BAR_SFREE + w * 8);
      mbar_wait(sb + BAR_DUMPS + w * 8, 1);
#pragma unroll 1
      for (int j = 0; j < 4; j++) {
        mbar_wait_soft(sb + BAR_EMPTY + (2 * j + w) * 8, 0);
        bulk_store(g_H + (r * 56 + 4 * c + j) * 16384 + w * 8192, s0 + j * 16384, 8192);
      }
      bulk_commit_wait();
      mbar_arrive(sb + BAR_SFREE + w * 8);
      flag_set(flags + 64 + 2 * c + w, tag);
      mbar_wait(sb + BAR_DUMPS + w * 8, 0);
#pragma unroll 1
      for (int j = 0; j < 3; j++) {
        const int i = HP * (2 * j + w);
        mbar_wait_soft(sb + BAR_EMPTY + (i & 7) * 8, (i >> 3) & 1);
        bulk_store(g_H + (r * 56 + 32 + 3 * c + j) * 16384 + w * 8192, s0 + j * 16384, 8192);
      }
      bulk_commit_wait();
      flag_set(flags + 64 + 16 + 2 * c + w, tag);
      fence_async_global();
      mbar_expect_tx(sb + BAR_RESH + w * 8, 16384);
      bulk_load(s0, g_h + (r * 16 + 2 * c) * 16384 + w * 8192, 8192, sb + BAR_RESH + w * 8);
      __nanosleep(700);
      bulk_load(s0 + 16384, g_h + (r * 16 + 2 * c + 1) * 16384 + w * 8192, 8192, sb + BAR_RESH + w * 8);
      if (w == 0) G.epoch[slot] = tag;
    }
  } else if (warp >= 8) {
    asm volatile("setmaxnreg.dec.sync.aligned.u32 104;");
    const int e = warp - 8, t = tid - 256;
    const uint32_t tag = get_tag(G.epoch + slot);
    const uint32_t S = sb + OFF_S;
    mbar_wait(sb + BAR_FULL, 0);
    if (e < 3) {
      const float2 y = colsum64(wqkv + r * (64 * 3072) + e * 1024 + c * 64, 3072, lane);
      ll_st4(&g_cs[c * 2048 + r * 128 + e * 32 + (lane & 7) * 4 + (lane >> 3)], y.x, y.y, tag);
    }
    if (t == 0) PROF(24);
    if (t == 0) sts_f(sb + OFF_TAG, __uint_as_float(tag));
    {
      const int row = c * 16 + (t >> 3);
      const bf16* p = x + (size_t)(2 * (s2base + row) + par) * 1024 + (lane & 7) * 8;
      uint4 v[16];
#pragma unroll
      for (int q = 0; q < 16; q++) v[q] = ldg_u4(p + q * 64);
      float s[4] = {0.f, 0.f, 0.f, 0.f};
#pragma unroll
      for (int q = 0; q < 16; q++) mom8(v[q], s);
      s[0] += s[1]; s[2] += s[3];
#pragma unroll
      for (int o = 1; o < 8; o <<= 1) { s[0] += __shfl_xor_sync(0xffffffffu, s[0], o); s[2] += __shfl_xor_sync(0xffffffffu, s[2], o); }
      const float mean = s[0] * (1.f / 1024.f);
      float m0 = fmaf(-mean, s[0], s[2]);
      if (__any_sync(0xffffffffu, !(m0 * 32.f >= s[2]))) {
        m0 = 0.f;
#pragma unroll 1
        for (int q = 0; q < 16; q++) sq8(ldg_u4(p + q * 64), mean, m0);
#pragma unroll
        for (int o = 1; o < 8; o <<= 1) m0 += __shfl_xor_sync(0xffffffffu, m0, o);
      }
      if ((lane & 7) == 0) ll_st4(&g_stats[r * 128 + row], mean, rsqrtf(m0 * (1.f / 1024.f) + 1e-5f), tag);
    }
    if (t == 0) PROF(20);
    if (e < 3) colsum_gather<16>(g_cs + c * 2048, sb + OFF_CS, t, tag);
    {
      float a, b; uint32_t spin = 0;
      while (!ll_ld4(&g_stats[r * 128 + t], a, b, tag)) { if (++spin > SPIN_LIMIT) __trap(); __nanosleep(200); }
      sts_f(sb + OFF_MEAN + t * 4, -a); sts_f(sb + OFF_RSTD + t * 4, b);
      __syncwarp();
    }
    float rq = 0.f, rkey = 0.f;
    arrive_elect(sb + BAR_E2C, 1);
    if (t == 0) PROF(21);
    if (r & 7) {
      float a; uint32_t spin = 0;
      while (!(ll_ld4(&g_stats[r * 128 + ((t >> 3) & 7)], a, rq, tag) & ll_ld4(&g_stats[r * 128 + ((t >> 3) & 7) + (t & 7) - 7], a, rkey, tag))) {
        if (++spin > SPIN_LIMIT) __trap();
        __nanosleep(200);
      }
      rq *= ATT_SC;
      __syncwarp();
    }
    uint4* const box = reinterpret_cast<uint4*>(g_halo) + ((r & 7) ? r - 1 : 16 + (r >> 3)) * 2048;
    const uint32_t opos = ((t >> 3) & 7) * 128 + ((((t >> 6) * 4 + ((t & 7) >> 1)) ^ ((t >> 3) & 7)) << 4) + (t & 1) * 8;
#pragma unroll 1
    for (int wave = 0; wave < 2; wave++) {
      const uint32_t ha = sb + ((e >> 1) ? OFF_V : OFF_K) - 1024 + (lane & 7) * 128 + (((((e & 1) * 4 + (lane >> 3)) ^ lane) & 7) << 4);
      uint2* src = g_halo + ((slot + 8 - 8 * wave) * 16 + e * 4) * 32 + lane;
      const uint32_t tw = tag ^ (wave << 30);
      uint32_t hv[4], spin = 0;
      mbar_wait(sb + BAR_QKV, wave);
      if ((r & 7) != 7) {
        ldsm4(ha + 16384, hv);
#pragma unroll
        for (int j = 0; j < 4; j++) ll_st2(src + j * 32, hv[j], tw);
      }
      if ((r & 7) != 0) {
        const int row = (t >> 3) & 7, h4 = (t >> 6) * 4, j = t & 7, kr = row + 1 + j;
        float qf[32];
#pragma unroll
        for (int q = 0; q < 4; q++) {
          const uint4 a = lds_u4(sb + OFF_Q + row * 128 + (((h4 + q) ^ row) << 4));
          qf[q * 8] = bf_lo(a.x); qf[q * 8 + 1] = bf_hi(a.x); qf[q * 8 + 2] = bf_lo(a.y); qf[q * 8 + 3] = bf_hi(a.y);
          qf[q * 8 + 4] = bf_lo(a.z); qf[q * 8 + 5] = bf_hi(a.z); qf[q * 8 + 6] = bf_lo(a.w); qf[q * 8 + 7] = bf_hi(a.w);
        }
#pragma unroll
        for (int q = 0; q < 32; q++) asm volatile("" : "+f"(qf[q]));
        if (wave == 0) __nanosleep(300);
        while (true) {
          bool ok = true;
#pragma unroll
          for (int j = 0; j < 4; j++) ok &= ll_ld2(src - 8 * 512 + j * 32, hv[j], tw);
          if (__all_sync(0xffffffffu, ok)) break;
          if (++spin > SPIN_LIMIT) __trap();
        }
        stsm4(ha, hv[0], hv[1], hv[2], hv[3]);
        bar_sync(3, 128);
        if (t == 0) PROF(22 + wave * 4);
        float s0 = 0.f, s1 = 0.f;
#pragma unroll
        for (int q = 0; q < 4; q++) {
          const uint4 b = lds_u4(sb + OFF_K - 1024 + kr * 128 + ((((h4 + q) ^ kr) & 7) << 4));
          s0 = fmaf(qf[q * 8], bf_lo(b.x), s0); s1 = fmaf(qf[q * 8 + 1], bf_hi(b.x), s1);
          s0 = fmaf(qf[q * 8 + 2], bf_lo(b.y), s0); s1 = fmaf(qf[q * 8 + 3], bf_hi(b.y), s1);
          s0 = fmaf(qf[q * 8 + 4], bf_lo(b.z), s0); s1 = fmaf(qf[q * 8 + 5], bf_hi(b.z), s1);
          s0 = fmaf(qf[q * 8 + 6], bf_lo(b.w), s0); s1 = fmaf(qf[q * 8 + 7], bf_hi(b.w), s1);
        }
        uint2 vv[8];
#pragma unroll
        for (int m = 0; m < 8; m++) vv[m] = lds_u2(sb + OFF_V - 1024 + (row + 1 + m) * 128 + ((((h4 + (j >> 1)) ^ (row + 1 + m)) & 7) << 4) + (j & 1) * 8);
        s0 = (s0 + s1) * rkey;
        float mx = s0;
#pragma unroll
        for (int o = 1; o < 8; o <<= 1) mx = fmaxf(mx, __shfl_xor_sync(0xffffffffu, mx, o));
        const float p = ex2((s0 - mx) * rq), pk = p * rkey;
        float o0 = 0.f, o1 = 0.f, o2 = 0.f, o3 = 0.f, sum = p;
#pragma unroll
        for (int o = 1; o < 8; o <<= 1) sum += __shfl_xor_sync(0xffffffffu, sum, o);
#pragma unroll
        for (int m = 0; m < 8; m++) {
          const float pm = __shfl_sync(0xffffffffu, pk, (lane & 24) + m);
          o0 = fmaf(pm, bf_lo(vv[m].x), o0); o1 = fmaf(pm, bf_hi(vv[m].x), o1); o2 = fmaf(pm, bf_lo(vv[m].y), o2); o3 = fmaf(pm, bf_hi(vv[m].y), o3);
        }
        const float inv = rcp(sum);
        const uint32_t w0 = pack2(o0 * inv, o1 * inv), w1 = pack2(o2 * inv, o3 * inv);
        if (wave == 1) ll_st4(box + c * 256 + t, __uint_as_float(w0), __uint_as_float(w1), tag ^ 0x80000000u);
        mbar_wait(sb + BAR_OATT, wave);
        if (wave == 1) mbar_wait(sb + BAR_FULL, 0);
        sts_u2(S + opos, w0, w1);
        fence_async_smem();
        bar_sync(3, 128);
      } else {
        mbar_wait(sb + BAR_OATT, wave);
        bar_sync(3, 128);
      }
      if (t == 0) {
        if (wave == 0) mbar_arrive(sb + BAR_O2);
        else {
          mbar_wait(sb + BAR_FULL, 0);
          mbar_arrive(sb + BAR_FULL);
        }
        PROF(23 + wave * 4);
      }
      __syncwarp();
      if (wave == 0) {
        if (e < 3) colsum_gather<1>(g_cs2 + c * 128, sb + OFF_CS + 768, t, tag);
        arrive_elect(sb + BAR_E2C, 1);
      }
    }
    {
      const uint32_t kw = ((c ^ 1) | (others(c) << 4)) >> (4 * e), e0 = P.ta[41];
      const uint32_t pos = sb + (lane >> 3) * 128 + ((((lane & 7) >> 1) ^ (lane >> 3)) << 4) + (lane & 1) * 8;
#pragma unroll 1
      for (int z = 0; z < (e < 3 ? 2 : 1); z++) {
        const uint32_t en = P.ta[41 + e + 4 * z];
        if (r & 7) {
          const uint4* src = box + ((kw >> (16 * z)) & 7) * 256 + lane;
          float a[4], b[4];
          for (uint32_t spin = 0;; spin++) {
            bool ok = true;
#pragma unroll
            for (int q = 0; q < 4; q++) ok &= ll_ld4(src + q * 32, a[q], b[q], tag ^ 0x80000000u);
            if (__all_sync(0xffffffffu, ok)) break;
            if (spin > SPIN_LIMIT) __trap();
          }
          if (z == 0) mbar_wait(sb + BAR_EMPTY + (e0 & 0x38), e0 >> 31);
          mbar_wait(sb + BAR_EMPTY + (en & 0x38), en >> 31);
#pragma unroll
          for (int q = 0; q < 4; q++) sts_f2((en & 0x3e000) + (q & 1) * 512 + (pos ^ (((q ^ (q >> 1)) & 1) * 64)), a[q], b[q]);
          fence_async_smem();
          complete_elect(sb + BAR_FULL + ((en >> 6) & 0x38), 1024);
        } else {
          mbar_wait_soft(sb + BAR_EMPTY + (en & 0x38), en >> 31);
        }
        if (t == 0 && z == 0) PROF(29);
        if ((e & 1) && z == 0 && lane == 0) {
          if (e == 1) mbar_expect_tx(sb + BAR_RESX, 32768);
          tma3d(S + 16384 + (e >> 1) * 16384, &P.x, sb + BAR_RESX, c * 128 + (e >> 1) * 64, par, s2base);
        }
        __syncwarp();
      }
    }
    mbar_wait(sb + BAR_DUMPS + (e >> 1) * 8, 0);
    {
      const uint32_t a = S + 16384 + t * 128;
      float s[4] = {0.f, 0.f, 0.f, 0.f};
#pragma unroll 4
      for (int q = 0; q < 8; q++) { mom8(lds_u4(a + ((q ^ t) & 7) * 16), s); mom8(lds_u4(a + 16384 + ((q ^ t) & 7) * 16), s); }
      s[0] += s[1]; s[2] += s[3];
      const float mean = s[0] * (1.f / 128.f);
      float m0 = fmaf(-mean, s[0], s[2]);
      if (!(m0 * 32.f >= s[2])) {
        m0 = 0.f;
#pragma unroll 1
        for (int q = 0; q < 16; q++) sq8(lds_u4(a + (q >> 3) * 16384 + ((q ^ t) & 7) * 16), mean, m0);
      }
      ll_st4(box + c * 256 + 128 + t, mean, m0, tag ^ 0x80000000u);
      __syncwarp();
#pragma unroll 1
      for (int k = 0; k < 2; k++)
        if (e < 4 - k) colsum_gather<1>(g_cs2 + (8 + k * 8 + c) * 128, sb + OFF_CS + k * 1024, t, tag);
      float mu[8], m2[8];
      uint32_t spin = 0;
      while (true) {
        __nanosleep(200);
        bool ok = true;
#pragma unroll
        for (int j = 0; j < 8; j++) ok &= ll_ld4(box + j * 256 + 128 + t, mu[j], m2[j], tag ^ 0x80000000u);
        if (ok) break;
        if (++spin > SPIN_LIMIT) __trap();
      }
      float mm = 0.f;
#pragma unroll
      for (int j = 0; j < 8; j++) mm += mu[j];
      mm *= 0.125f;
      float var = 0.f;
#pragma unroll
      for (int j = 0; j < 8; j++) { const float d = mu[j] - mm; var += fmaf(128.f * d, d, m2[j]); }
      sts_f(sb + OFF_MEAN + t * 4, -mm); sts_f(sb + OFF_RSTD + t * 4, rsqrtf(var * (1.f / 1024.f) + 1e-5f));
    }
    __syncwarp();
    arrive_elect(sb + BAR_E2C, 1);
    if (t == 0) {
      PROF(28);
#pragma unroll 1
      for (int j = PFN - 2; j < 7; j++) { bulk_prefetch((const uint8_t*)w2 + slot * 57344 + j * 8192, 8192); __nanosleep(600); }
    }
  } else {
    asm volatile("setmaxnreg.inc.sync.aligned.u32 184;");
    if (tid == 0) PROF(44);
    const int wg = warp >> 2;
    if (P.sched[1] == 0xffff) __trap();
    const uint32_t sb2 = is_paired(sb) ? peer(sb) : sb;
    const uint32_t S = sb + OFF_S;
    const uint32_t frag = S + (warp * 16 + ((lane >> 3) & 1) * 8 + (lane & 7)) * 128;
    const uint32_t xq = (uint32_t)((lane >> 4) ^ (lane & 7)) << 4;
    const uint32_t rowoff = (warp * 16 + (lane >> 2)) * 4;
    const uint32_t csa = sb + OFF_CS + (lane & 3) * 16;
    const uint32_t xk = (uint32_t)((lane >> 3) ^ (lane & 7)) << 4;
    const uint32_t rk = (uint32_t)(lane & 7) * 128;
    const uint32_t kv = sb + (warp * 16 + (lane >> 4) * 8) * 128 + rk + ((((lane >> 3) & 1) ^ (lane & 7)) << 4);
    const bool early0 = (lane & 3) * 2 > (lane >> 2), early1 = (lane & 3) * 2 + 1 > (lane >> 2);
    const uint32_t me = (early0 ? 0xffffu : 0u) | (early1 ? 0xffff0000u : 0u);
    float nm0, nm1, rs0, rs1;
#pragma unroll 1
    for (int wave = 0; wave < 2; wave++) {
      float acc[96];
      mainloop<3, true>(acc, P, sb, sb2, wg, wave * 16, 16, slot);
      mbar_wait(sb + BAR_E2C, wave);
      if (tid == 0) PROF(14 + wave * 2);
      nm0 = lds_f(sb + OFF_MEAN + rowoff); nm1 = lds_f(sb + OFF_MEAN + rowoff + 32);
      rs0 = lds_f(sb + OFF_RSTD + rowoff); rs1 = lds_f(sb + OFF_RSTD + rowoff + 32);
      rs0 *= ATT_SC; rs1 *= ATT_SC;
      const uint32_t ra = sb + OFF_RSTD + warp * 64 + (lane & 3) * 8;
      const float kr[4] = {lds_f(ra - (early0 ? 32 : 0)), lds_f(ra + 4 - (early1 ? 32 : 0)), lds_f(ra + 32 - (early0 ? 32 : 0)), lds_f(ra + 36 - (early1 ? 32 : 0))};
      float4 cs[12];
#pragma unroll
      for (int jj = 0; jj < 12; jj++) cs[jj] = lds_f4(csa + wave * 768 + jj * 64);
      if (wave == 1) mbar_wait(sb + BAR_OFREE, 0);
      mainloop_end<((XC >> 0) & 1) != 0>(acc, sb, sb2, sb + BAR_E2C, wave);
      if (tid == 0) PROF(2 + wave * 2);
      uint32_t lo[16], hi[16];
#pragma unroll
      for (int jj = 0; jj < 12; jj++) {
        const int j = ((jj + 4) % 12) * 2;
        const float4 cc = cs[j >> 1];
        const uint32_t p0 = pack2(fmaf(nm0, cc.x, acc[4 * j]), fmaf(nm0, cc.y, acc[4 * j + 1]));
        const uint32_t p1 = pack2(fmaf(nm1, cc.x, acc[4 * j + 2]), fmaf(nm1, cc.y, acc[4 * j + 3]));
        const uint32_t p2 = pack2(fmaf(nm0, cc.z, acc[4 * j + 4]), fmaf(nm0, cc.w, acc[4 * j + 5]));
        const uint32_t p3 = pack2(fmaf(nm1, cc.z, acc[4 * j + 6]), fmaf(nm1, cc.w, acc[4 * j + 7]));
        if (j >= 8) stsm4((j < 16 ? OFF_K : OFF_V) + (kv ^ ((j & 7) << 4)), p0, p2, p1, p3);
        if (j < 16) { lo[j] = p0; hi[j] = p1; lo[j + 1] = p2; hi[j + 1] = p3; }
      }
      if (warp == 0) {
#pragma unroll
        for (int j = 0; j < 8; j += 2) stsm4(frag + (OFF_Q - OFF_S) + (xq ^ (j << 4)), lo[j], hi[j], lo[j + 1], hi[j + 1]);
      }
      bar_sync(4, 256);
      if (warp == 3) arrive_elect(sb + BAR_QKV, 1);
      if (tid == 0) PROF(15 + wave * 2);
      const uint32_t ka = sb + OFF_K - 1024 + warp * 2048 + rk;
      uint32_t k0[2][4], v0[2][4], v1[2][4], v2[2][4];
      float s0[2][4], s1[2][4], s2[2][4];
#pragma unroll
      for (int hh = 0; hh < 2; hh++) ldsm4(ka + (xk ^ (hh * 64)), k0[hh]);
#pragma unroll
      for (int hh = 0; hh < 2; hh++) {
        ldsm4t(ka + (OFF_V - OFF_K) + (xk ^ (hh * 64)), v0[hh]);
        ldsm4t(ka + (OFF_V - OFF_K) + 1024 + (xk ^ (hh * 64)), v1[hh]);
        ldsm4t(ka + (OFF_V - OFF_K) + 2048 + (xk ^ (hh * 64)), v2[hh]);
#pragma unroll
        for (int q = 0; q < 4; q++) s0[hh][q] = s1[hh][q] = s2[hh][q] = 0.f;
      }
#pragma unroll
      for (int ks = 0; ks < 2; ks++) {
#pragma unroll
        for (int hh = 0; hh < 2; hh++) {
          const int q = hh * 4 + ks * 2;
          mma16816(s1[hh], lo[q], hi[q], lo[q + 1], hi[q + 1], lo[8 + q], lo[9 + q]);
          mma16816(s2[hh], lo[q], hi[q], lo[q + 1], hi[q + 1], hi[8 + q], hi[9 + q]);
        }
      }
#pragma unroll
      for (int ks = 0; ks < 2; ks++) {
#pragma unroll
        for (int hh = 0; hh < 2; hh++) {
          const int q = hh * 4 + ks * 2;
          mma16816(s0[hh], lo[q], hi[q], lo[q + 1], hi[q + 1], k0[hh][ks * 2], k0[hh][ks * 2 + 1]);
        }
      }
      float a0[4], a1[4], mx[4], sum[4];
      uint32_t pp[4];
#pragma unroll
      for (int hh = 0; hh < 2; hh++) {
        a0[2 * hh] = (early0 ? s0[hh][0] : s1[hh][0]) * kr[0]; a1[2 * hh] = (early1 ? s0[hh][1] : s1[hh][1]) * kr[1];
        a0[2 * hh + 1] = (early0 ? s1[hh][2] : s2[hh][2]) * kr[2]; a1[2 * hh + 1] = (early1 ? s1[hh][3] : s2[hh][3]) * kr[3];
        if (warp == 0) {
          if (early0) a0[2 * hh] = __int_as_float(0xff800000);
          if (early1) a1[2 * hh] = __int_as_float(0xff800000);
          v0[hh][0] = v0[hh][1] = v0[hh][2] = v0[hh][3] = 0u;
        }
      }
#pragma unroll
      for (int q = 0; q < 4; q++) { mx[q] = fmaxf(a0[q], a1[q]); mx[q] = fmaxf(mx[q], __shfl_xor_sync(0xffffffffu, mx[q], 1)); }
#pragma unroll
      for (int q = 0; q < 4; q++) mx[q] = fmaxf(mx[q], __shfl_xor_sync(0xffffffffu, mx[q], 2));
#pragma unroll
      for (int q = 0; q < 4; q++) {
        const float sc = (q & 1) ? rs1 : rs0, e0 = ex2((a0[q] - mx[q]) * sc), e1 = ex2((a1[q] - mx[q]) * sc);
        pp[q] = pack2(e0 * kr[(q & 1) * 2], e1 * kr[(q & 1) * 2 + 1]);
        sum[q] = e0 + e1;
      }
      float o[2][4][4];
#pragma unroll
      for (int hh = 0; hh < 2; hh++) {
#pragma unroll
        for (int n = 0; n < 4; n++) {
          o[hh][n][0] = o[hh][n][1] = o[hh][n][2] = o[hh][n][3] = 0.f;
          mma16816(o[hh][n], pp[2 * hh] & me, 0u, pp[2 * hh] & ~me, pp[2 * hh + 1] & me, v0[hh][n], v1[hh][n]);
        }
      }
#pragma unroll
      for (int q = 0; q < 4; q++) sum[q] += __shfl_xor_sync(0xffffffffu, sum[q], 1);
#pragma unroll
      for (int hh = 0; hh < 2; hh++) {
#pragma unroll
        for (int n = 0; n < 4; n++) mma1688(o[hh][n], 0u, pp[2 * hh + 1] & ~me, v2[hh][n]);
      }
#pragma unroll
      for (int q = 0; q < 4; q++) sum[q] = rcp(sum[q] + __shfl_xor_sync(0xffffffffu, sum[q], 2));
#pragma unroll
      for (int hh = 0; hh < 2; hh++) {
        const float ia = sum[2 * hh], ib = sum[2 * hh + 1];
#pragma unroll
        for (int n = 0; n < 4; n += 2)
          stsm4(frag + (xq ^ (hh * 64 + n * 16)), pack2(o[hh][n][0] * ia, o[hh][n][1] * ia), pack2(o[hh][n][2] * ib, o[hh][n][3] * ib),
                pack2(o[hh][n + 1][0] * ia, o[hh][n + 1][1] * ia), pack2(o[hh][n + 1][2] * ib, o[hh][n + 1][3] * ib));
      }
      fence_async_smem();
      arrive_elect(sb + BAR_OATT, 1);
      bar_sync(4, 256);
      if (tid == 0) PROF(3 + wave * 2);
    }
    {
      float acc[64];
      mainloop<2>(acc, P, sb, sb2, wg, 32, 16, slot);
      mbar_wait(sb + BAR_RESX, 0);
      uint32_t xr[8][4];
#pragma unroll
      for (int j = 0; j < 16; j += 2) ldsm4(frag + 16384 + (j >> 3) * 16384 + (xq ^ ((j & 7) << 4)), xr[j >> 1]);
      mainloop_end<((XC >> 1) & 1) != 0>(acc, sb, sb2, sb + BAR_RESX, 0);
      if (tid == 0) PROF(6);
#pragma unroll
      for (int j = 0; j < 16; j += 2) {
        const uint32_t* v = xr[j >> 1];
        stsm4(frag + 16384 + (j >> 3) * 16384 + (xq ^ ((j & 7) << 4)),
              pack2(acc[4 * j] + bf_lo(v[0]), acc[4 * j + 1] + bf_hi(v[0])), pack2(acc[4 * j + 2] + bf_lo(v[1]), acc[4 * j + 3] + bf_hi(v[1])),
              pack2(acc[4 * j + 4] + bf_lo(v[2]), acc[4 * j + 5] + bf_hi(v[2])), pack2(acc[4 * j + 6] + bf_lo(v[3]), acc[4 * j + 7] + bf_hi(v[3])));
        if (j == 6) { fence_async_smem(); arrive_elect(sb + BAR_DUMPH + wg * 8, 1); }
      }
      fence_async_smem();
      arrive_elect(sb + BAR_DUMPS + wg * 8, 1);
      bar_sync(1 + wg, 128);
      if (tid == 0) PROF(7);
    }
    {
      float acc[128];
      mainloop<4>(acc, P, sb, sb2, wg, 48, 16, slot);
      mbar_wait(sb + BAR_E2C, 0);
      if (tid == 0) PROF(18);
      mbar_wait(sb + BAR_SFREE + wg * 8, 0);
      nm0 = lds_f(sb + OFF_MEAN + rowoff); nm1 = lds_f(sb + OFF_MEAN + rowoff + 32);
      rs0 = lds_f(sb + OFF_RSTD + rowoff); rs1 = lds_f(sb + OFF_RSTD + rowoff + 32);
      float4 cs[16];
#pragma unroll
      for (int jj = 0; jj < 6; jj++) cs[jj] = lds_f4(csa + jj * 64);
      mainloop_end<((XC >> 2) & 1) != 0>(acc, sb, sb2, sb + BAR_SFREE + wg * 8, 0);
      if (tid == 0) PROF(8);
#pragma unroll
      for (int j = 0; j < 32; j += 2) {
        const float4 cc = cs[j >> 1];
        const uint32_t p0 = pack2_relu(fmaf(nm0, cc.x, acc[4 * j]), fmaf(nm0, cc.y, acc[4 * j + 1])), p1 = pack2_relu(fmaf(nm1, cc.x, acc[4 * j + 2]), fmaf(nm1, cc.y, acc[4 * j + 3]));
        const uint32_t p2 = pack2_relu(fmaf(nm0, cc.z, acc[4 * j + 4]), fmaf(nm0, cc.w, acc[4 * j + 5])), p3 = pack2_relu(fmaf(nm1, cc.z, acc[4 * j + 6]), fmaf(nm1, cc.w, acc[4 * j + 7]));
        if (j < 10) { cs[6 + j] = lds_f4(csa + (6 + j) * 64); cs[7 + j] = lds_f4(csa + (7 + j) * 64); }
        stsm4(frag + (j >> 3) * 16384 + (xq ^ ((j & 7) << 4)), p0, p1, p2, p3);
      }
      fence_async_smem();
      arrive_elect(sb + BAR_DUMPS + wg * 8, 1);
      if (tid == 0) PROF(9);
    }
    {
      float acc[96];
      mainloop<3>(acc, P, sb, sb2, wg, 64, 16, slot);
      mbar_wait(sb + BAR_SFREE + wg * 8, 1);
      float4 cs[12];
#pragma unroll
      for (int jj = 0; jj < 12; jj++) cs[jj] = lds_f4(csa + 1024 + jj * 64);
      mainloop_end<((XC >> 3) & 1) != 0>(acc, sb, sb2, sb + BAR_SFREE + wg * 8, 1);
      if (tid == 0) PROF(10);
#pragma unroll
      for (int j = 0; j < 24; j += 2) {
        const float4 cc = cs[j >> 1];
        stsm4(frag + (j >> 3) * 16384 + (xq ^ ((j & 7) << 4)),
              pack2_relu(fmaf(nm0, cc.x, acc[4 * j]), fmaf(nm0, cc.y, acc[4 * j + 1])), pack2_relu(fmaf(nm1, cc.x, acc[4 * j + 2]), fmaf(nm1, cc.y, acc[4 * j + 3])),
              pack2_relu(fmaf(nm0, cc.z, acc[4 * j + 4]), fmaf(nm0, cc.w, acc[4 * j + 5])), pack2_relu(fmaf(nm1, cc.z, acc[4 * j + 6]), fmaf(nm1, cc.w, acc[4 * j + 7])));
      }
      fence_async_smem();
      arrive_elect(sb + BAR_DUMPS + wg * 8, 1);
      if (tid == 0) PROF(11);
    }
    {
      float acc[64];
      mainloop<2>(acc, P, sb, sb2, wg, 80, 56, slot);
      mbar_wait(sb + BAR_RESH + wg * 8, 0);
      uint32_t hr[8][4];
#pragma unroll
      for (int j = 0; j < 16; j += 2) ldsm4(frag + (j >> 3) * 16384 + (xq ^ ((j & 7) << 4)), hr[j >> 1]);
      mainloop_end<((XC >> 4) & 1) != 0>(acc, sb, sb2, sb + BAR_RESH + wg * 8, 0);
      if (tid == 0) PROF(12);
#pragma unroll
      for (int j = 0; j < 16; j += 2) {
        const uint32_t* v = hr[j >> 1];
        stsm4(frag + (j >> 3) * 16384 + (xq ^ ((j & 7) << 4)),
              pack2(fmaf(acc[4 * j], rs0, bf_lo(v[0])), fmaf(acc[4 * j + 1], rs0, bf_hi(v[0]))), pack2(fmaf(acc[4 * j + 2], rs1, bf_lo(v[1])), fmaf(acc[4 * j + 3], rs1, bf_hi(v[1]))),
              pack2(fmaf(acc[4 * j + 4], rs0, bf_lo(v[2])), fmaf(acc[4 * j + 5], rs0, bf_hi(v[2]))), pack2(fmaf(acc[4 * j + 6], rs1, bf_lo(v[3])), fmaf(acc[4 * j + 7], rs1, bf_hi(v[3]))));
        if ((j & 7) == 6) {
          fence_async_smem();
          __syncwarp();
          if (lane == 0) tma3d_store(&P.out, S + (j >> 3) * 16384 + warp * 2048, c * 128 + (j >> 3) * 64, par, s2base + warp * 16);
        }
      }
      if (tid == 0) PROF(13);
      if (lane == 0) asm volatile("cp.async.bulk.commit_group;\ncp.async.bulk.wait_group.read 0;" ::: "memory");
      if (tid == 0) { PROF(31); PROFG(32); }
    }
  }
}

void make_schedule(Params& P) {
  int head = HEAD0, occ[RING_UNITS + 8];
  for (int u = 0; u < RING_UNITS + 8; u++) occ[u] = -100;
  for (int i = 0; i < 144; i++) {
    const int nb = i < 32 ? 3 : i < 48 ? 2 : i < 64 ? 4 : i < 80 ? 3 : 2;
    int off[2], lag[2];
    for (int op = 0; op < 2; op++) {
      const int sz = op == 0 ? nb : 2;
      lag[op] = 8;
      if (i >= 48 && i < 64) {
        static const int ub[4] = {12, 16, 0, 6}, ua[4] = {20, 26, 4, 10};
        head = 12;
        off[op] = op == 0 ? ub[i & 3] : i < 50 ? 22 + 2 * (i - 48) : ua[i & 3];
      } else if (R6 && i >= 80) {
        int best = 0;
        for (int u = 2; u < 28; u += 2) {
          if (u >= RING_UNITS && !(op == 1 && (u == 26 || (u == 24 && i >= 112)))) continue;
          if ((occ[u] > occ[u + 1] ? occ[u] : occ[u + 1]) < (occ[best] > occ[best + 1] ? occ[best] : occ[best + 1])) best = u;
        }
        off[op] = best;
      } else if (S5 && (i == 4 || i == 9)) {
        off[op] = RING_UNITS + 3 * op;
      } else if (op == 1 && i == 40) off[op] = RING_UNITS;
      else {
        if (head + sz > RING_UNITS) head = 0;
        off[op] = head;
        head += sz;
      }
      for (int u = off[op]; u < off[op] + sz; u++) { if (i - occ[u] < lag[op]) lag[op] = i - occ[u]; occ[u] = i; }
    }
    P.sched[i] = (uint16_t)(off[0] | (off[1] << 5));
    for (int op = 0; op < 2; op++) {
      const uint32_t ws = (uint32_t)(i - lag[op]);
      (op ? P.ta : P.tb)[i] = (ws & 7) * 8 | (i & 7) * 8 << 6 | off[op] * UNIT | ((ws >> 3) & 1) << 31;
    }
  }
}

typedef CUresult (*EncodeFn)(CUtensorMap*, CUtensorMapDataType, cuuint32_t, void*, const cuuint64_t*, const cuuint64_t*, const cuuint32_t*,
                             const cuuint32_t*, CUtensorMapInterleave, CUtensorMapSwizzle, CUtensorMapL2promotion, CUtensorMapFloatOOBfill);

void make_map(EncodeFn enc, CUtensorMap* m, const void* ptr, uint64_t d0, uint64_t d1, uint64_t d2, uint64_t s1, uint64_t s2,
              uint32_t b0, uint32_t b1, uint32_t b2) {
  cuuint64_t dims[3] = {d0, d1, d2}, strides[2] = {s1, s2};
  cuuint32_t box[3] = {b0, b1, b2}, es[3] = {1, 1, 1};
  enc(m, CU_TENSOR_MAP_DATA_TYPE_BFLOAT16, 3, const_cast<void*>(ptr), dims, strides, box, es, CU_TENSOR_MAP_INTERLEAVE_NONE,
      CU_TENSOR_MAP_SWIZZLE_128B, CU_TENSOR_MAP_L2_PROMOTION_L2_256B, CU_TENSOR_MAP_FLOAT_OOB_FILL_NONE);
}

}

extern "C" void kernel_launch(void* const* d_in, const int* in_sizes, int n_in, void* d_out, int out_size) {
  const bf16* x = (const bf16*)d_in[0];
  const bf16* wqkv = (const bf16*)d_in[1];
  const bf16* wo = (const bf16*)d_in[2];
  const bf16* w1 = (const bf16*)d_in[4];
  const bf16* w2 = (const bf16*)d_in[5];
  static EncodeFn enc = nullptr;
  static uint32_t* epoch = nullptr;
  if (!enc) {
    cudaGetSymbolAddress((void**)&epoch, g_epoch);
    void* p = nullptr;
    cudaDriverEntryPointQueryResult q;
    cudaGetDriverEntryPoint("cuTensorMapEncodeTiled", &p, cudaEnableDefault, &q);
    enc = (EncodeFn)p;
    cudaFuncSetAttribute(fused_block_kernel, cudaFuncAttributeMaxDynamicSharedMemorySize, SMEM_BYTES);
  }
  Params P;
  make_schedule(P);
  make_map(enc, &P.x, x, 1024, 2, 1024, 2048, 4096, 64, 1, 128);
  make_map(enc, &P.out, d_out, 1024, 2, 1024, 2048, 4096, 64, 1, 16);
  make_map(enc, &P.wqkv, wqkv, 1024, 1024, 3, 6144, 2048, 64, 64, 3);
  make_map(enc, &P.wo, wo, 64, 1024, 16, 2048, 128, 64, 64, 2);
  make_map(enc, &P.w1a, w1, 64, 1024, 56, 7168, 128, 64, 64, 4);
  make_map(enc, &P.w1b, w1, 64, 1024, 56, 7168, 128, 64, 64, 3);
  make_map(enc, &P.w2, w2, 64, 3584, 16, 2048, 128, 64, 64, 2);
  const Ptrs G = {{x, wqkv, wo, w2}, epoch};
  fused_block_kernel<<<132, 512, SMEM_BYTES>>>(G, P);
}
```
